```python
import torch

def _softmax(x, axis=-1):
    return torch.softmax(x, dim=axis)
def _gelu(x):
    return torch.nn.functional.gelu(x, approximate="tanh")
def _silu(x):
    return torch.nn.functional.silu(x)
def _sigmoid(x):
    return torch.sigmoid(x)
def _layernorm(x, axis=-1, eps=1e-5):
    m = x.mean(dim=axis, keepdim=True)
    v = x.var(dim=axis, keepdim=True, unbiased=False)
    return (x - m) / torch.sqrt(v + eps)
def _scatter_add(tgt, idx, src, axis=0):
    return tgt.clone().index_add_(axis, idx, src)
def _segment_sum(src, seg, n):
    out = torch.zeros((n,) + src.shape[1:], dtype=src.dtype)
    return out.index_add_(0, seg, src)
def _pad(x, pw):
    flat = tuple(v for pair in reversed(pw) for v in pair)
    return torch.nn.functional.pad(x, flat)

kernel_name = 'concat_heads__mha_block_cached__mha_block_cached__near_ridge'

def setup_inputs():

    _w = (lambda a: (lambda t: t.to(torch.bfloat16) if t.is_floating_point() else t)(torch.as_tensor(a)))
    def _A_setup():
        B, Sq, D = 16, 160, 1024
        H, Sk, Dh = 32, 512, 128
        return {
            "x": _w((lambda *s: torch.randn(*s, dtype=torch.bfloat16) * 0.8)(B, Sq, D)),
            "k_cache": _w((lambda *s: torch.randn(*s, dtype=torch.bfloat16) * 0.8)(B, H, Sk, Dh)),
            "v_cache": _w((lambda *s: torch.randn(*s, dtype=torch.bfloat16) * 0.05)(B, H, Sk, Dh)),
            "wq": _w((lambda *s: torch.randn(*s, dtype=torch.bfloat16) * 0.8)(D, H * Dh) * (D ** -0.5)),
            "wo": _w((lambda *s: torch.randn(*s, dtype=torch.bfloat16) * 0.05)(H * Dh, D) * ((H * Dh) ** -0.5)),
        }
    _A_in = _A_setup()

    def _B_setup():
        B, Sq, D = 16, 160, 1024
        H, Sk, Dh = 32, 512, 128
        return {
            "x": _w((lambda *s: torch.randn(*s, dtype=torch.bfloat16) * 0.8)(B, Sq, D)),
            "k_cache": _w((lambda *s: torch.randn(*s, dtype=torch.bfloat16) * 0.8)(B, H, Sk, Dh)),
            "v_cache": _w((lambda *s: torch.randn(*s, dtype=torch.bfloat16) * 0.05)(B, H, Sk, Dh)),
            "wq": _w((lambda *s: torch.randn(*s, dtype=torch.bfloat16) * 0.8)(D, H * Dh) * (D ** -0.5)),
            "wo": _w((lambda *s: torch.randn(*s, dtype=torch.bfloat16) * 0.05)(H * Dh, D) * ((H * Dh) ** -0.5)),
        }
    _B_in = _B_setup()

    return {
        "A_x": _A_in["x"],
        "A_k_cache": _A_in["k_cache"],
        "A_v_cache": _A_in["v_cache"],
        "A_wq": _A_in["wq"],
        "A_wo": _A_in["wo"],
        "B_x": _B_in["x"],
        "B_k_cache": _B_in["k_cache"],
        "B_v_cache": _B_in["v_cache"],
        "B_wq": _B_in["wq"],
        "B_wo": _B_in["wo"],
    }

def reference(A_x, A_k_cache, A_v_cache, A_wq, A_wo, B_x, B_k_cache, B_v_cache, B_wq, B_wo):
    def _A_ref(x, k_cache, v_cache, wq, wo):
        B, Sq, D = x.shape
        H, Dh = 32, 128
        q = (lambda x, *d: x.permute(*d))((x @ wq).reshape(B, Sq, H, Dh), 0, 2, 1, 3)
        scores = torch.einsum("bhqd,bhkd->bhqk", q, k_cache) * (Dh ** -0.5)
        p = _softmax(scores, axis=-1)
        o = torch.einsum("bhqk,bhkd->bhqd", p, v_cache)
        return (lambda x, *d: x.permute(*d))(o, 0, 2, 1, 3).reshape(B, Sq, H * Dh) @ wo

    def _B_ref(x, k_cache, v_cache, wq, wo):
        B, Sq, D = x.shape
        H, Dh = 32, 128
        q = (lambda x, *d: x.permute(*d))((x @ wq).reshape(B, Sq, H, Dh), 0, 2, 1, 3)
        scores = torch.einsum("bhqd,bhkd->bhqk", q, k_cache) * (Dh ** -0.5)
        p = _softmax(scores, axis=-1)
        o = torch.einsum("bhqk,bhkd->bhqd", p, v_cache)
        return (lambda x, *d: x.permute(*d))(o, 0, 2, 1, 3).reshape(B, Sq, H * Dh) @ wo

    a = _A_ref(A_x, A_k_cache, A_v_cache, A_wq, A_wo)
    b = _B_ref(B_x, B_k_cache, B_v_cache, B_wq, B_wo)
    return torch.concatenate([a, b], axis=-1)
```

```cpp
#include <cuda_runtime.h>
#include <cuda_bf16.h>
#include <cuda.h>
#include <stdint.h>
#include <stdio.h>

namespace mha {

constexpr int ROWS = 2560;
constexpr int HD = 4096;
constexpr int NTHREADS = 512;
constexpr int QHALF = 40960;
constexpr int QREG = 2 * QHALF;
constexpr int GSTAGE = 57344;
constexpr int GX = 40960;
constexpr int KVSTAGE = 16384;
constexpr int DATA_BYTES = 4 * GSTAGE;
constexpr int NB = 16;
constexpr int SMEM_BYTES = DATA_BYTES + 1024;

struct alignas(64) Params {
  CUtensorMap x[2], wq[2], kc[2], vc[2], wo[2], o_st, o_ld, out_st;
  int offload;
};

__device__ __nv_bfloat16 g_o[2 * ROWS * HD];
__device__ uint4 g_qspill[64 * (QREG / 16)];
__device__ unsigned int g_cnt[16 * 4];
__device__ unsigned int g_qready[64];
__device__ unsigned int g_done[16 * 4];

__device__ __forceinline__ uint32_t smem_u32(const void* p) { return (uint32_t)__cvta_generic_to_shared(p); }
__device__ __forceinline__ void mbar_init(uint32_t bar, int cnt) {
  asm volatile("mbarrier.init.shared::cta.b64 [%0], %1;" ::"r"(bar), "r"(cnt));
}
__device__ __forceinline__ void mbar_expect_tx(uint32_t bar, uint32_t bytes) {
  asm volatile("mbarrier.arrive.expect_tx.shared::cta.b64 _, [%0], %1;" ::"r"(bar), "r"(bytes) : "memory");
}
__device__ __forceinline__ void mbar_arrive(uint32_t bar) {
  asm volatile("mbarrier.arrive.shared::cta.b64 _, [%0];" ::"r"(bar) : "memory");
}
__device__ __forceinline__ void mbar_wait(uint32_t bar, uint32_t parity) {
  asm volatile("{\n.reg .pred P1;\n.reg .u32 n;\nmov.u32 n, 0;\n"
               "LAB_WAIT:\n"
               "mbarrier.try_wait.parity.shared::cta.b64 P1, [%0], %1;\n"
               "@P1 bra.uni DONE;\n"
               "add.u32 n, n, 1;\n"
               "setp.lt.u32 P1, n, 1048576;\n"
               "@P1 bra.uni LAB_WAIT;\n"
               "DONE:\n}" ::"r"(bar), "r"(parity) : "memory");
}
__device__ __forceinline__ bool mbar_test(uint32_t bar, uint32_t parity) {
  uint32_t ok;
  asm volatile("{\n.reg .pred P1;\nmbarrier.test_wait.parity.shared::cta.b64 P1, [%1], %2;\nselp.b32 %0, 1, 0, P1;\n}"
               : "=r"(ok) : "r"(bar), "r"(parity) : "memory");
  return ok != 0;
}
__device__ __forceinline__ void mbar_arrive_cluster(uint32_t bar, uint32_t cta) {
  asm volatile("{\n.reg .b32 ra;\nmapa.shared::cluster.u32 ra, %0, %1;\nmbarrier.arrive.shared::cluster.b64 _, [ra];\n}"
               ::"r"(bar), "r"(cta) : "memory");
}
__device__ __forceinline__ void tma2d_mc(uint32_t dst, const CUtensorMap* tm, int c0, int c1, uint32_t bar) {
  asm volatile("cp.async.bulk.tensor.2d.shared::cluster.global.mbarrier::complete_tx::bytes.multicast::cluster"
               " [%0], [%1, {%3, %4}], [%2], %5;"
               ::"r"(dst), "l"(tm), "r"(bar), "r"(c0), "r"(c1), "h"((uint16_t)3) : "memory");
}
__device__ __forceinline__ void tma3d(uint32_t dst, const CUtensorMap* tm, int c0, int c1, int c2, uint32_t bar) {
  asm volatile("cp.async.bulk.tensor.3d.shared::cluster.global.mbarrier::complete_tx::bytes"
               " [%0], [%1, {%3, %4, %5}], [%2];"
               ::"r"(dst), "l"(tm), "r"(bar), "r"(c0), "r"(c1), "r"(c2) : "memory");
}
__device__ __forceinline__ void tma3d_hint(uint32_t dst, const CUtensorMap* tm, int c0, int c1, int c2, uint32_t bar, uint64_t pol) {
  asm volatile("cp.async.bulk.tensor.3d.shared::cluster.global.mbarrier::complete_tx::bytes.L2::cache_hint"
               " [%0], [%1, {%3, %4, %5}], [%2], %6;"
               ::"r"(dst), "l"(tm), "r"(bar), "r"(c0), "r"(c1), "r"(c2), "l"(pol) : "memory");
}
__device__ __forceinline__ void tma2d_store(const CUtensorMap* tm, uint32_t src, int c0, int c1) {
  asm volatile("cp.async.bulk.tensor.2d.global.shared::cta.bulk_group [%0, {%2, %3}], [%1];"
               ::"l"(tm), "r"(src), "r"(c0), "r"(c1) : "memory");
}
__device__ __forceinline__ void tma2d_store_hint(const CUtensorMap* tm, uint32_t src, int c0, int c1, uint64_t pol) {
  asm volatile("cp.async.bulk.tensor.2d.global.shared::cta.bulk_group.L2::cache_hint [%0, {%2, %3}], [%1], %4;"
               ::"l"(tm), "r"(src), "r"(c0), "r"(c1), "l"(pol) : "memory");
}
__device__ __forceinline__ void bulk_store(void* gdst, uint32_t src, uint32_t bytes) {
  asm volatile("cp.async.bulk.global.shared::cta.bulk_group [%0], [%1], %2;" ::"l"(gdst), "r"(src), "r"(bytes) : "memory");
}
__device__ __forceinline__ void bulk_load(uint32_t dst, const void* gsrc, uint32_t bytes, uint32_t bar) {
  asm volatile("cp.async.bulk.shared::cluster.global.mbarrier::complete_tx::bytes [%0], [%1], %2, [%3];"
               ::"r"(dst), "l"(gsrc), "r"(bytes), "r"(bar) : "memory");
}
__device__ __forceinline__ void bulk_commit() { asm volatile("cp.async.bulk.commit_group;" ::: "memory"); }
__device__ __forceinline__ void bulk_wait0() { asm volatile("cp.async.bulk.wait_group 0;" ::: "memory"); }
__device__ __forceinline__ void bulk_wait0_read() { asm volatile("cp.async.bulk.wait_group.read 0;" ::: "memory"); }
__device__ __forceinline__ void fence_async_smem() { asm volatile("fence.proxy.async.shared::cta;" ::: "memory"); }
__device__ __forceinline__ void fence_async_all() { asm volatile("fence.proxy.async;" ::: "memory"); }
__device__ __forceinline__ void bar_sync(int id, int n) { asm volatile("bar.sync %0, %1;" ::"r"(id), "r"(n) : "memory"); }
__device__ __forceinline__ void bar_arrive(int id, int n) { asm volatile("bar.arrive %0, %1;" ::"r"(id), "r"(n) : "memory"); }
__device__ __forceinline__ void wg_fence() { asm volatile("wgmma.fence.sync.aligned;" ::: "memory"); }
__device__ __forceinline__ void wg_commit() { asm volatile("wgmma.commit_group.sync.aligned;" ::: "memory"); }
template <int N> __device__ __forceinline__ void wg_wait() { asm volatile("wgmma.wait_group.sync.aligned %0;" ::"n"(N) : "memory"); }
template <int N>
__device__ __forceinline__ void fence_regs(float (&d)[N]) {
#pragma unroll
  for (int i = 0; i < N; i++) asm volatile("" : "+f"(d[i])::"memory");
}
__device__ __forceinline__ uint32_t desc_lo(uint32_t addr, uint32_t lbo) { return (addr >> 4) + ((lbo >> 4) << 16); }
__device__ __forceinline__ uint32_t uni(uint32_t v) { return __shfl_sync(0xffffffffu, v, 0); }
__device__ __forceinline__ uint32_t pack_bf16(float lo, float hi) {
  uint32_t r;
  asm("cvt.rn.bf16x2.f32 %0, %1, %2;" : "=r"(r) : "f"(hi), "f"(lo));
  return r;
}
__device__ __forceinline__ float ex2(float x) {
  float y;
  asm("ex2.approx.ftz.f32 %0, %1;" : "=f"(y) : "f"(x));
  return y;
}
__device__ __forceinline__ void stmatrix4(uint32_t addr, uint32_t r0, uint32_t r1, uint32_t r2, uint32_t r3) {
  asm volatile("stmatrix.sync.aligned.m8n8.x4.shared.b16 [%0], {%1, %2, %3, %4};"
               ::"r"(addr), "r"(r0), "r"(r1), "r"(r2), "r"(r3) : "memory");
}

template <int TA, int TB>
__device__ __forceinline__ void wgmma_ss128(float (&d)[64], uint32_t da, uint32_t db) {
  asm volatile("{\n.reg .pred p;\n.reg .b64 da, db;\nsetp.eq.b32 p, 0, 0;\n"
    "mov.b64 da, {%64, 0x40000040};\nmov.b64 db, {%65, 0x40000040};\n"
    "wgmma.mma_async.sync.aligned.m64n128k16.f32.bf16.bf16 "
    "{%0, %1, %2, %3, %4, %5, %6, %7, %8, %9, %10, %11, %12, %13, %14, %15, %16, %17, %18, %19, %20, %21, %22, %23, %24, %25, %26, %27, %28, %29, %30, %31, %32, %33, %34, %35, %36, %37, %38, %39, %40, %41, %42, %43, %44, %45, %46, %47, %48, %49, %50, %51, %52, %53, %54, %55, %56, %57, %58, %59, %60, %61, %62, %63}, "
    "da, db, p, 1, 1, %66, %67;\n}\n"
    : "+f"(d[0]), "+f"(d[1]), "+f"(d[2]), "+f"(d[3]), "+f"(d[4]), "+f"(d[5]), "+f"(d[6]), "+f"(d[7]), "+f"(d[8]), "+f"(d[9]), "+f"(d[10]), "+f"(d[11]), "+f"(d[12]), "+f"(d[13]), "+f"(d[14]), "+f"(d[15]), "+f"(d[16]), "+f"(d[17]), "+f"(d[18]), "+f"(d[19]), "+f"(d[20]), "+f"(d[21]), "+f"(d[22]), "+f"(d[23]), "+f"(d[24]), "+f"(d[25]), "+f"(d[26]), "+f"(d[27]), "+f"(d[28]), "+f"(d[29]), "+f"(d[30]), "+f"(d[31]), "+f"(d[32]), "+f"(d[33]), "+f"(d[34]), "+f"(d[35]), "+f"(d[36]), "+f"(d[37]), "+f"(d[38]), "+f"(d[39]), "+f"(d[40]), "+f"(d[41]), "+f"(d[42]), "+f"(d[43]), "+f"(d[44]), "+f"(d[45]), "+f"(d[46]), "+f"(d[47]), "+f"(d[48]), "+f"(d[49]), "+f"(d[50]), "+f"(d[51]), "+f"(d[52]), "+f"(d[53]), "+f"(d[54]), "+f"(d[55]), "+f"(d[56]), "+f"(d[57]), "+f"(d[58]), "+f"(d[59]), "+f"(d[60]), "+f"(d[61]), "+f"(d[62]), "+f"(d[63])
    : "r"(da), "r"(db), "n"(TA), "n"(TB));
}

template <int TA, int TB>
__device__ __forceinline__ void wgmma_ss64(float (&d)[32], uint32_t da, uint32_t db) {
  asm volatile("{\n.reg .pred p;\n.reg .b64 da, db;\nsetp.eq.b32 p, 0, 0;\n"
    "mov.b64 da, {%32, 0x40000040};\nmov.b64 db, {%33, 0x40000040};\n"
    "wgmma.mma_async.sync.aligned.m64n64k16.f32.bf16.bf16 "
    "{%0, %1, %2, %3, %4, %5, %6, %7, %8, %9, %10, %11, %12, %13, %14, %15, %16, %17, %18, %19, %20, %21, %22, %23, %24, %25, %26, %27, %28, %29, %30, %31}, "
    "da, db, p, 1, 1, %34, %35;\n}\n"
    : "+f"(d[0]), "+f"(d[1]), "+f"(d[2]), "+f"(d[3]), "+f"(d[4]), "+f"(d[5]), "+f"(d[6]), "+f"(d[7]), "+f"(d[8]), "+f"(d[9]), "+f"(d[10]), "+f"(d[11]), "+f"(d[12]), "+f"(d[13]), "+f"(d[14]), "+f"(d[15]), "+f"(d[16]), "+f"(d[17]), "+f"(d[18]), "+f"(d[19]), "+f"(d[20]), "+f"(d[21]), "+f"(d[22]), "+f"(d[23]), "+f"(d[24]), "+f"(d[25]), "+f"(d[26]), "+f"(d[27]), "+f"(d[28]), "+f"(d[29]), "+f"(d[30]), "+f"(d[31])
    : "r"(da), "r"(db), "n"(TA), "n"(TB));
}

template <int TA, int TB>
__device__ __forceinline__ void wgmma_ss64_init(float (&d)[32], uint32_t da, uint32_t db) {
  asm volatile("{\n.reg .pred p;\n.reg .b64 da, db;\nsetp.ne.b32 p, 0, 0;\n"
    "mov.b64 da, {%32, 0x40000040};\nmov.b64 db, {%33, 0x40000040};\n"
    "wgmma.mma_async.sync.aligned.m64n64k16.f32.bf16.bf16 "
    "{%0, %1, %2, %3, %4, %5, %6, %7, %8, %9, %10, %11, %12, %13, %14, %15, %16, %17, %18, %19, %20, %21, %22, %23, %24, %25, %26, %27, %28, %29, %30, %31}, "
    "da, db, p, 1, 1, %34, %35;\n}\n"
    : "=f"(d[0]), "=f"(d[1]), "=f"(d[2]), "=f"(d[3]), "=f"(d[4]), "=f"(d[5]), "=f"(d[6]), "=f"(d[7]), "=f"(d[8]), "=f"(d[9]), "=f"(d[10]), "=f"(d[11]), "=f"(d[12]), "=f"(d[13]), "=f"(d[14]), "=f"(d[15]), "=f"(d[16]), "=f"(d[17]), "=f"(d[18]), "=f"(d[19]), "=f"(d[20]), "=f"(d[21]), "=f"(d[22]), "=f"(d[23]), "=f"(d[24]), "=f"(d[25]), "=f"(d[26]), "=f"(d[27]), "=f"(d[28]), "=f"(d[29]), "=f"(d[30]), "=f"(d[31])
    : "r"(da), "r"(db), "n"(TA), "n"(TB));
}

template <int TB>
__device__ __forceinline__ void wgmma_rs128(float (&d)[64], uint32_t a0, uint32_t a1, uint32_t a2, uint32_t a3, uint32_t db) {
  asm volatile("{\n.reg .pred p;\n.reg .b64 db;\nsetp.eq.b32 p, 0, 0;\n"
    "mov.b64 db, {%68, 0x40000040};\n"
    "wgmma.mma_async.sync.aligned.m64n128k16.f32.bf16.bf16 "
    "{%0, %1, %2, %3, %4, %5, %6, %7, %8, %9, %10, %11, %12, %13, %14, %15, %16, %17, %18, %19, %20, %21, %22, %23, %24, %25, %26, %27, %28, %29, %30, %31, %32, %33, %34, %35, %36, %37, %38, %39, %40, %41, %42, %43, %44, %45, %46, %47, %48, %49, %50, %51, %52, %53, %54, %55, %56, %57, %58, %59, %60, %61, %62, %63}, "
    "{%64, %65, %66, %67}, db, p, 1, 1, %69;\n}\n"
    : "+f"(d[0]), "+f"(d[1]), "+f"(d[2]), "+f"(d[3]), "+f"(d[4]), "+f"(d[5]), "+f"(d[6]), "+f"(d[7]), "+f"(d[8]), "+f"(d[9]), "+f"(d[10]), "+f"(d[11]), "+f"(d[12]), "+f"(d[13]), "+f"(d[14]), "+f"(d[15]), "+f"(d[16]), "+f"(d[17]), "+f"(d[18]), "+f"(d[19]), "+f"(d[20]), "+f"(d[21]), "+f"(d[22]), "+f"(d[23]), "+f"(d[24]), "+f"(d[25]), "+f"(d[26]), "+f"(d[27]), "+f"(d[28]), "+f"(d[29]), "+f"(d[30]), "+f"(d[31]), "+f"(d[32]), "+f"(d[33]), "+f"(d[34]), "+f"(d[35]), "+f"(d[36]), "+f"(d[37]), "+f"(d[38]), "+f"(d[39]), "+f"(d[40]), "+f"(d[41]), "+f"(d[42]), "+f"(d[43]), "+f"(d[44]), "+f"(d[45]), "+f"(d[46]), "+f"(d[47]), "+f"(d[48]), "+f"(d[49]), "+f"(d[50]), "+f"(d[51]), "+f"(d[52]), "+f"(d[53]), "+f"(d[54]), "+f"(d[55]), "+f"(d[56]), "+f"(d[57]), "+f"(d[58]), "+f"(d[59]), "+f"(d[60]), "+f"(d[61]), "+f"(d[62]), "+f"(d[63])
    : "r"(a0), "r"(a1), "r"(a2), "r"(a3), "r"(db), "n"(TB));
}


extern __shared__ __align__(1024) uint8_t smem_raw[];
#define SBASE (smem_u32(smem_raw))
#define DBASE (SBASE & 0x3FFFFu)
#define QBASE (SBASE)
#define FULL0 (SBASE + DATA_BYTES)
#define EMPTY0 (FULL0 + NB * 8)
#define OSTAGED (EMPTY0 + NB * 8)
#define QFREE (OSTAGED + 24)
#define QLD (QFREE + 8)
#define Q0FREE (QLD + 16)

__device__ __forceinline__ int wg_tid() { int v; asm volatile("mov.u32 %0, %%tid.x;" : "=r"(v)); return v & 127; }

__device__ __forceinline__ int op_kblock(bool late, bool offl, int i) {
  if (late && !offl) return i == 0 ? 3 : (i == 1 ? 0 : (i == 2 ? 2 : 1));
  return i == 0 ? 2 : (i == 1 ? 3 : (i == 2 ? 1 : 0));
}
__device__ __forceinline__ uint32_t gemm_off(int s) { return (uint32_t)((0x0132 >> ((s & 3) * 4)) & 3) * GSTAGE; }
constexpr uint32_t KV_SPECIAL = QHALF;
__device__ __forceinline__ uint32_t kv_off(int n) { return QREG + (uint32_t)((n + 2) & 7) * KVSTAGE; }

struct BarSeq {
  uint32_t cnt;
  __device__ __forceinline__ void next(uint32_t& boff, uint32_t& par) {
    par = cnt / NB;
    boff = (cnt % NB) * 8;
    cnt = (cnt + 1) % (2 * NB);
  }
};

__device__ __forceinline__ uint32_t make_rel() {
  const int t = threadIdx.x & 127;
  uint32_t ra = 0;
  if (t < 2) asm volatile("mapa.shared::cluster.u32 %0, %1, %2;" : "=r"(ra) : "r"(EMPTY0), "r"(t));
  return ra;
}
__device__ __forceinline__ uint32_t rel_local(uint32_t rel) {
  return rel ? ((rel & 0x00FFFFFFu) | (SBASE & 0xFF000000u)) : 0u;
}
__device__ __forceinline__ void release_stage(uint32_t rel, uint32_t boff) {
  asm volatile("{\n.reg .pred p;\nsetp.ne.u32 p, %0, 0;\n@p mbarrier.arrive.shared::cluster.b64 _, [%1];\n}"
               ::"r"(rel), "r"(rel + boff) : "memory");
}

template <bool SCALE>
__device__ __forceinline__ void store_tile(const float (&a)[64], int row0, float s0, float s1, int half1 = QHALF) {
  const int t = wg_tid();
  const int lane = t & 31, warp = t >> 5;
  const int mi = lane >> 3;
  const int r = row0 + warp * 16 + (mi & 1) * 8 + (lane & 7);
  const uint32_t rowaddr = QBASE + r * 128;
  const uint32_t x = ((mi >> 1) ^ (lane & 7)) << 4;
#pragma unroll
  for (int q = 0; q < 8; q++) {
    const uint32_t addr = rowaddr + (q >> 2) * half1 + (x ^ ((2 * (q & 3)) << 4));
    if (SCALE)
      stmatrix4(addr, pack_bf16(a[8 * q + 0] * s0, a[8 * q + 1] * s0), pack_bf16(a[8 * q + 2] * s1, a[8 * q + 3] * s1),
                pack_bf16(a[8 * q + 4] * s0, a[8 * q + 5] * s0), pack_bf16(a[8 * q + 6] * s1, a[8 * q + 7] * s1));
    else
      stmatrix4(addr, pack_bf16(a[8 * q + 0], a[8 * q + 1]), pack_bf16(a[8 * q + 2], a[8 * q + 3]),
                pack_bf16(a[8 * q + 4], a[8 * q + 5]), pack_bf16(a[8 * q + 6], a[8 * q + 7]));
  }
}

constexpr int BAR_ALL = 4;

template <int NT>
__device__ __forceinline__ void gemm_phase(BarSeq& bs, int nst, int nrel, int tile0, uint32_t rel) {
  float acc0[64], acc1[64];
#pragma unroll
  for (int i = 0; i < 64; i++) { acc0[i] = 0.f; acc1[i] = 0.f; }
  uint32_t prev = 0;
  uint32_t b, par;
  bs.next(b, par);
  mbar_wait(FULL0 + b, par);
  for (int s = 0; s < nst; s++) {
    const uint32_t st = DBASE + gemm_off(s);
    const uint32_t da = desc_lo(st + tile0 * 8192, 16);
    const uint32_t db = desc_lo(st + GX, 8192);
    const uint32_t cur = b;
    bool ready = true;
    if (s + 1 < nst) {
      bs.next(b, par);
      ready = mbar_test(FULL0 + b, par);
    }
    fence_regs(acc0);
    if (NT == 2) fence_regs(acc1);
    wg_fence();
    wgmma_ss128<0, 1>(acc0, da, db);
    if (NT == 2) wgmma_ss128<0, 1>(acc1, da + 512, db);
    wg_commit();
    if (s > 0) {
      wg_wait<1>();
      if (s < nrel) release_stage(rel, prev);
    }
    wg_fence();
#pragma unroll
    for (int kk = 1; kk < 4; kk++) {
      wgmma_ss128<0, 1>(acc0, da + kk * 2, db + kk * 128);
      if (NT == 2) wgmma_ss128<0, 1>(acc1, da + 512 + kk * 2, db + kk * 128);
    }
    wg_commit();
    prev = cur;
    if (!__all_sync(0xffffffffu, ready)) mbar_wait(FULL0 + b, par);
  }
  wg_wait<0>();
  if (nst < nrel) release_stage(rel, prev);
  fence_regs(acc0);
  if (NT == 2) fence_regs(acc1);
  bar_sync(BAR_ALL, 384);
  store_tile<false>(acc0, tile0 * 64, 1.f, 1.f);
  if (NT == 2) store_tile<false>(acc1, tile0 * 64 + 64, 1.f, 1.f);
  fence_async_smem();
}

__device__ __forceinline__ bool wg_all(int id, bool v) {
  uint32_t r;
  asm volatile("{\n.reg .pred p, q;\nsetp.ne.u32 q, %1, 0;\nbar.red.and.pred p, %2, 128, q;\nselp.u32 %0, 1, 0, p;\n}"
               : "=r"(r) : "r"((uint32_t)v), "r"(id) : "memory");
  return __all_sync(0xffffffffu, r != 0);
}
__device__ __forceinline__ void issue_qk(float (&S)[32], uint32_t dq, uint32_t dk) {
  wgmma_ss64_init<0, 0>(S, dq, dk);
#pragma unroll
  for (int ks = 1; ks < 8; ks++)
    wgmma_ss64<0, 0>(S, dq + (ks >> 2) * (QHALF >> 4) + (ks & 3) * 2, dk + (ks >> 2) * 512 + (ks & 3) * 2);
}
__device__ __forceinline__ void issue_pv(float (&O)[64], const uint32_t (&P)[16], uint32_t dv) {
#pragma unroll
  for (int ks = 0; ks < 4; ks++)
    wgmma_rs128<1>(O, P[4 * ks], P[4 * ks + 1], P[4 * ks + 2], P[4 * ks + 3], dv + ks * 128);
}

constexpr float SC = 0.08838834764831845f * 1.4426950408889634f;
constexpr float SAFE = 1.0995116e12f;

__device__ __forceinline__ void row_max(const float (&S)[32], float& m0, float& m1) {
  float mx0 = fmaxf(S[0], S[1]), mx1 = fmaxf(S[2], S[3]);
  float mx0b = fmaxf(S[4], S[5]), mx1b = fmaxf(S[6], S[7]);
#pragma unroll
  for (int i = 2; i < 8; i += 2) {
    mx0 = fmaxf(mx0, fmaxf(S[4 * i], S[4 * i + 1]));
    mx1 = fmaxf(mx1, fmaxf(S[4 * i + 2], S[4 * i + 3]));
    mx0b = fmaxf(mx0b, fmaxf(S[4 * i + 4], S[4 * i + 5]));
    mx1b = fmaxf(mx1b, fmaxf(S[4 * i + 6], S[4 * i + 7]));
  }
  mx0 = fmaxf(mx0, mx0b); mx1 = fmaxf(mx1, mx1b);
  mx0 = fmaxf(mx0, __shfl_xor_sync(0xffffffffu, mx0, 1));
  mx1 = fmaxf(mx1, __shfl_xor_sync(0xffffffffu, mx1, 1));
  mx0 = fmaxf(mx0, __shfl_xor_sync(0xffffffffu, mx0, 2));
  mx1 = fmaxf(mx1, __shfl_xor_sync(0xffffffffu, mx1, 2));
  m0 = fmaxf(m0, mx0 * SC);
  m1 = fmaxf(m1, mx1 * SC);
}
__device__ __forceinline__ void exp_tile(const float (&S)[32], float m0, float m1, uint32_t (&P)[16], float& s0, float& s1) {
  float s0a = 0.f, s0b = 0.f, s1a = 0.f, s1b = 0.f;
#pragma unroll
  for (int i = 0; i < 8; i++) {
    const float p0 = ex2(fmaf(S[4 * i + 0], SC, -m0)), p1 = ex2(fmaf(S[4 * i + 1], SC, -m0));
    const float p2 = ex2(fmaf(S[4 * i + 2], SC, -m1)), p3 = ex2(fmaf(S[4 * i + 3], SC, -m1));
    s0a += p0; s0b += p1; s1a += p2; s1b += p3;
    P[2 * i] = pack_bf16(p0, p1);
    P[2 * i + 1] = pack_bf16(p2, p3);
  }
  s0 = s0a + s0b; s1 = s1a + s1b;
}

__device__ __forceinline__ void kv_wait(uint32_t c0, int n) {
  const uint32_t c = (c0 + n) % (2 * NB);
  mbar_wait(FULL0 + (c % NB) * 8, c / NB);
}
__device__ __forceinline__ bool kv_try(uint32_t c0, int n) {
  const uint32_t c = (c0 + n) % (2 * NB);
  return mbar_test(FULL0 + (c % NB) * 8, c / NB);
}
__device__ __forceinline__ void kv_release(uint32_t rel, uint32_t c0, int n) { release_stage(rel, ((c0 + n) % NB) * 8); }

__device__ __forceinline__ void att_stage(const float (&O)[64], bool valid, int qrow, float l0, float l1, int half1 = QHALF) {
  l0 += __shfl_xor_sync(0xffffffffu, l0, 1);
  l1 += __shfl_xor_sync(0xffffffffu, l1, 1);
  l0 += __shfl_xor_sync(0xffffffffu, l0, 2);
  l1 += __shfl_xor_sync(0xffffffffu, l1, 2);
  float i0, i1;
  asm("rcp.approx.ftz.f32 %0, %1;" : "=f"(i0) : "f"(l0));
  asm("rcp.approx.ftz.f32 %0, %1;" : "=f"(i1) : "f"(l1));
  if (valid) store_tile<true>(O, qrow, i0, i1, half1);
}
__device__ __forceinline__ void att_publish(int wg) {
  fence_async_smem();
  mbar_arrive(OSTAGED + wg * 8);
}

__device__ __forceinline__ bool att_step(uint32_t rel, uint32_t c0, int u, int nloc, bool last, bool special, bool publish, bool valid, int wg,
                                         uint32_t dq, float (&O)[64], const uint32_t (&Pin)[16], uint32_t (&Pout)[16],
                                         float m0, float m1, float& l0, float& l1) {
  float S[32];
  const int nk = 2 * u;
  const uint32_t rl = (nk < nloc) ? rel_local(rel) : rel, rlv = (nk - 1 < nloc) ? rel_local(rel) : rel;
  wg_fence();
  issue_qk(S, dq, desc_lo(DBASE + kv_off(nk), 16));
  wg_commit();
  issue_pv(O, Pin, desc_lo(DBASE + (special ? KV_SPECIAL : kv_off(nk - 1)), 8192));
  wg_commit();
  if (publish) att_publish(wg);
  const bool ready = (last || kv_try(c0, nk + 2)) & kv_try(c0, nk + 1);
  wg_wait<1>();
  fence_regs(S);
  float s0, s1;
  if (valid) {
    exp_tile(S, m0, m1, Pout, s0, s1);
  } else {
    s0 = 0.f; s1 = 0.f;
#pragma unroll
    for (int i = 0; i < 16; i++) Pout[i] = 0u;
  }
  const bool ok = wg_all(5 + wg, s0 < SAFE && s1 < SAFE);
  if (ok) { l0 += s0; l1 += s1; kv_release(rl, c0, nk); }
  wg_wait<0>();
  fence_regs(O);
  kv_release(rlv, c0, nk - 1);
  if (!__all_sync(0xffffffffu, ready)) {
    if (!last) kv_wait(c0, nk + 2);
    kv_wait(c0, nk + 1);
  }
  return ok;
}

template <bool ORDERED>
__device__ __forceinline__ void att_first(uint32_t c0, int u0, int wg, uint32_t dq, uint32_t (&P)[16], float& m0, float& m1,
                                          float& l0, float& l1) {
  float S[32];
  kv_wait(c0, 2 * u0);
  if (ORDERED && wg > 0) bar_sync(wg, 256);
  wg_fence();
  issue_qk(S, dq, desc_lo(DBASE + kv_off(2 * u0), 16));
  wg_commit();
  if (ORDERED && wg < 2) bar_arrive(wg + 1, 256);
  kv_wait(c0, 2 * u0 + 2);
  kv_wait(c0, 2 * u0 + 1);
  wg_wait<0>();
  fence_regs(S);
  m0 = -INFINITY; m1 = -INFINITY;
  row_max(S, m0, m1);
  exp_tile(S, m0, m1, P, l0, l1);
}

__device__ __forceinline__ void attention_phase(BarSeq& bs, int wg, uint32_t rel, int nb, bool helper) {
  const uint32_t c0 = bs.cnt;
  const int nloc = helper ? 16 * nb : 16 * nb - 8;
  const int qld0 = helper ? 0 : 2;
  const bool valid = wg < 2 || uni(wg_tid() >> 5) < 2;
  bs.cnt = (c0 + 16 * nb) % (2 * NB);
  float O[64];
  uint32_t Pa[16], Pb[16];
  float m0, m1, l0, l1;
  if (helper) mbar_wait(QLD, 0);
  att_first<true>(c0, 0, wg, desc_lo(DBASE + wg * 64 * 128, 16), Pa, m0, m1, l0, l1);
  kv_release(rel_local(rel), c0, 0);
  bool pend = false;
#pragma unroll 1
  for (int bb = 0; bb < nb; bb++) {
    const int u0 = bb * 8;
    const int qrow = (bb & 1) * 160 + wg * 64;
    const uint32_t dq = desc_lo(DBASE + qrow * 128, 16);
    const uint32_t dqn = desc_lo(DBASE + (((bb + 1) & 1) * 160 + wg * 64) * 128, 16);
#pragma unroll
    for (int i = 0; i < 64; i++) O[i] = 0.f;
    fence_regs(O);
    int jfail;
#pragma unroll 1
    for (int j = 1; j < 7; j += 2) {
      if (!att_step(rel, c0, u0 + j, nloc, false, false, j == 1 && pend, valid, wg, dq, O, Pa, Pb, m0, m1, l0, l1)) { jfail = j; goto slow; }
      if (!att_step(rel, c0, u0 + j + 1, nloc, false, false, false, valid, wg, dq, O, Pb, Pa, m0, m1, l0, l1)) { jfail = j + 1; goto slow; }
    }
    if (!att_step(rel, c0, u0 + 7, nloc, bb == nb - 1, bb == nb - 1 && !helper, false, valid, wg, dq, O, Pa, Pb, m0, m1, l0, l1)) { jfail = 7; goto slow; }
    if (bb < nb - 1) {
      float S[32];
      if (bb + 1 >= qld0) mbar_wait(QLD + ((bb + 1) & 1) * 8, ((bb + 1 - qld0) >> 1) & 1);
      wg_fence();
      issue_qk(S, dqn, desc_lo(DBASE + kv_off(2 * u0 + 16), 16));
      wg_commit();
      issue_pv(O, Pb, desc_lo(DBASE + kv_off(2 * u0 + 15), 8192));
      wg_commit();
      const bool rdy = kv_try(c0, 2 * u0 + 18) & kv_try(c0, 2 * u0 + 17);
      wg_wait<1>();
      fence_regs(S);
      kv_release(rel_local(rel), c0, 2 * u0 + 16);
      float n0, n1;
      m0 = -INFINITY; m1 = -INFINITY;
      row_max(S, m0, m1);
      exp_tile(S, m0, m1, Pa, n0, n1);
      wg_wait<0>();
      fence_regs(O);
      kv_release(rel_local(rel), c0, 2 * u0 + 15);
      att_stage(O, valid, qrow, l0, l1);
      l0 = n0; l1 = n1;
      pend = true;
      if (!__all_sync(0xffffffffu, rdy)) { kv_wait(c0, 2 * u0 + 18); kv_wait(c0, 2 * u0 + 17); }
    } else {
      wg_fence();
      issue_pv(O, Pb, desc_lo(DBASE + kv_off(2 * u0 + 15), 8192));
      wg_commit();
      wg_wait<0>();
      fence_regs(O);
      kv_release(helper ? rel_local(rel) : rel, c0, 2 * u0 + 15);
      att_stage(O, valid, qrow, l0, l1, helper ? QHALF : -160 * 128);
      att_publish(wg);
    }
    continue;
  slow:
    {
#pragma unroll 1
      for (int u = u0 + jfail; u < u0 + 8; u++) {
        float S[32];
        kv_wait(c0, 2 * u);
        wg_fence();
        issue_qk(S, dq, desc_lo(DBASE + kv_off(2 * u), 16));
        wg_commit();
        wg_wait<0>();
        fence_regs(S);
        kv_release(2 * u < nloc ? rel_local(rel) : rel, c0, 2 * u);
        const float o0 = m0, o1 = m1;
        row_max(S, m0, m1);
        const float sc0 = ex2(o0 - m0), sc1 = ex2(o1 - m1);
        float s0, s1;
        exp_tile(S, m0, m1, Pa, s0, s1);
        l0 = l0 * sc0 + s0; l1 = l1 * sc1 + s1;
#pragma unroll
        for (int i = 0; i < 16; i++) {
          O[4 * i + 0] *= sc0; O[4 * i + 1] *= sc0; O[4 * i + 2] *= sc1; O[4 * i + 3] *= sc1;
        }
        kv_wait(c0, 2 * u + 1);
        fence_regs(O);
        wg_fence();
        issue_pv(O, Pa, desc_lo(DBASE + ((!helper && 2 * u + 1 == 16 * nb - 3) ? KV_SPECIAL : kv_off(2 * u + 1)), 8192));
        wg_commit();
        wg_wait<0>();
        fence_regs(O);
        kv_release(2 * u + 1 < nloc ? rel_local(rel) : rel, c0, 2 * u + 1);
      }
      att_stage(O, valid, qrow, l0, l1, (bb == nb - 1 && !helper) ? -160 * 128 : QHALF);
      att_publish(wg);
      if (bb < nb - 1) {
        if (bb + 1 >= qld0) mbar_wait(QLD + ((bb + 1) & 1) * 8, ((bb + 1 - qld0) >> 1) & 1);
        att_first<false>(c0, u0 + 8, wg, dqn, Pa, m0, m1, l0, l1);
        kv_release(rel_local(rel), c0, 2 * u0 + 16);
      }
      pend = false;
    }
  }
}

__global__ void __cluster_dims__(2, 1, 1) __launch_bounds__(NTHREADS, 1)
fused_mha_kernel(const __grid_constant__ Params prm) {
  const int tid = threadIdx.x;
  const int wg = __shfl_sync(0xffffffffu, tid >> 7, 0);
  if (SBASE & 1023) __trap();

  if (tid == 384) {
    const int b = (blockIdx.x >> 6) ? 1 : 0;
    asm volatile("prefetch.tensormap [%0];" ::"l"(&prm.x[b]) : "memory");
    asm volatile("prefetch.tensormap [%0];" ::"l"(&prm.wq[b]) : "memory");
    asm volatile("prefetch.tensormap [%0];" ::"l"(&prm.kc[b]) : "memory");
    asm volatile("prefetch.tensormap [%0];" ::"l"(&prm.vc[b]) : "memory");
  }
  if (tid == 0) {
    for (int s = 0; s < NB; s++) { mbar_init(FULL0 + s * 8, 1); mbar_init(EMPTY0 + s * 8, 6); }
    for (int s = 0; s < 3; s++) mbar_init(OSTAGED + s * 8, 128);
    mbar_init(QFREE, 2);
    mbar_init(QLD, 1);
    mbar_init(QLD + 8, 1);
    mbar_init(Q0FREE, 1);
    asm volatile("fence.mbarrier_init.release.cluster;" ::: "memory");
  }
  __syncthreads();
  asm volatile("barrier.cluster.arrive.relaxed.aligned;\nbarrier.cluster.wait.aligned;" ::: "memory");

  if (wg == 3) {
    asm volatile("setmaxnreg.dec.sync.aligned.u32 32;");
    const int g = blockIdx.x >> 3, j = blockIdx.x & 7;
    const int blk = g >> 3, p = g & 7;
    const uint32_t rank = blockIdx.x & 1;
    const bool helper = blockIdx.x >= 128;
    const bool late = blk == 1;
    const bool offl = late && prm.offload && p >= 4;
    if (helper) {
      const int hp = 4 + (blockIdx.x - 128), hg = 8 + hp;
      if (tid == 384) {
        uint64_t pol;
        asm volatile("createpolicy.fractional.L2::evict_first.b64 %0, 1.0;" : "=l"(pol));
#pragma unroll 1
        for (uint32_t n = 0; n < 256; n++) {
          if (n >= 8) mbar_wait(EMPTY0 + ((n - 8) % NB) * 8, ((n - 8) / NB) & 1);
          const int kvrow = ((2 * hp + ((n >> 4) & 1)) * 32 + (n >> 5)) * 512 + ((n >> 1) & 7) * 64;
          const uint32_t fb = FULL0 + (n % NB) * 8;
          mbar_expect_tx(fb, KVSTAGE);
          tma3d_hint(SBASE + kv_off(n), (n & 1) ? &prm.vc[1] : &prm.kc[1], 0, kvrow, 0, fb, pol);
        }
      } else if (tid == 416) {
        uint64_t spol;
        asm volatile("createpolicy.fractional.L2::evict_first.b64 %0, 1.0;" : "=l"(spol));
        const uint8_t* qs = reinterpret_cast<const uint8_t*>(g_qspill) + (size_t)(hp * 8) * QREG;
        auto load_q = [&](int bb) {
          if (!(bb & 1)) {
            unsigned int* f = &g_qready[hp * 8 + (bb >> 1)];
            unsigned int v; int n = 0;
            do {
              asm volatile("ld.acquire.gpu.global.u32 %0, [%1];" : "=r"(v) : "l"(f) : "memory");
            } while (v == 0u && ++n < (1 << 22));
            *f = 0;
            fence_async_all();
          }
          const uint32_t o = (bb & 1) * 20480;
          const uint8_t* src = qs + (size_t)(bb >> 1) * QREG;
          mbar_expect_tx(QLD + (bb & 1) * 8, 40960);
          bulk_load(QBASE + o, src + o, 20480, QLD + (bb & 1) * 8);
          bulk_load(QBASE + QHALF + o, src + QHALF + o, 20480, QLD + (bb & 1) * 8);
        };
        load_q(0);
        load_q(1);
#pragma unroll 1
        for (int bb = 0; bb < 16; bb++) {
          const int ocol = (bb >> 1) * 128, orow = ROWS + hp * 320;
          for (int w = 0; w < 3; w++) {
            mbar_wait(OSTAGED + w * 8, bb & 1);
            const int np = (w < 2) ? 2 : 1;
            for (int pc = 0; pc < np; pc++) {
              const int rr = (bb & 1) * 160 + w * 64 + pc * 32;
              tma2d_store_hint(&prm.o_st, QBASE + rr * 128, ocol, orow + rr, spol);
              tma2d_store_hint(&prm.o_st, QBASE + QHALF + rr * 128, ocol + 64, orow + rr, spol);
            }
            bulk_commit();
          }
          if (bb + 2 < 16) {
            bulk_wait0_read();
            load_q(bb + 2);
          }
          if (bb & 1) {
            bulk_wait0();
            fence_async_all();
            __threadfence();
            asm volatile("red.release.gpu.global.add.u32 [%0], 1;" ::"l"(&g_cnt[hg * 4]) : "memory");
          }
        }
      }
    } else if (tid == 384) {
      uint64_t pol;
      asm volatile("createpolicy.fractional.L2::evict_first.b64 %0, 1.0;" : "=l"(pol));
      uint32_t seq = 0, rel = 0, natt = 0;
      auto need = [&](uint32_t d) {
        while (rel <= d) {
          mbar_wait(EMPTY0 + (rel % NB) * 8, (rel / NB) & 1);
          rel++;
        }
      };
      const CUtensorMap* tk = &prm.kc[blk];
      const CUtensorMap* tv = &prm.vc[blk];
#pragma unroll 1
      for (int r = 0; r <= 4; r++) {
        const bool op = (r == 4);
        const bool prev_kv = r > 0 && !(late && r == 1);
        const CUtensorMap* ta = op ? &prm.o_ld : &prm.x[blk];
        const CUtensorMap* tw = op ? &prm.wo[blk] : &prm.wq[blk];
        const int arow = (op ? blk * ROWS : 0) + p * 320 + rank * 160;
        const int wcol = op ? j * 2 : (r * 8 + j) * 2;
        const int nst = op ? 64 : 16;
#pragma unroll 1
        for (int s = 0; s < nst; s++) {
          const uint32_t off = gemm_off(s);
          if (r > 0 && s == (prev_kv ? 3 : 2)) mbar_wait(QFREE, (r - 1) & 1);
          if (s >= 4 || (r > 0 && !prev_kv)) need(seq - 4);
          else if (prev_kv) {
            if (s < 2) need(seq - 5);
            else if (s == 2) need(seq - 3);
          }
          const uint32_t fb = FULL0 + (seq % NB) * 8;
          mbar_expect_tx(fb, GSTAGE);
          int kcol = s * 64;
          const int tq = op_kblock(late, offl, s >> 4);
          if (op) kcol = tq * 1024 + (s & 15) * 64;
          tma3d(SBASE + off + GX, tw, 0, kcol, wcol, fb);
          if (op && (s & 15) == 0) {
            unsigned int* cnt = &g_cnt[g * 4 + tq];
            unsigned int v; int n = 0;
            do {
              asm volatile("ld.acquire.gpu.global.u32 %0, [%1];" : "=r"(v) : "l"(cnt) : "memory");
            } while (v < 8u && ++n < (1 << 22));
            fence_async_all();
            if (atomicAdd(&g_done[g * 4 + tq], 1u) == 7u) { g_done[g * 4 + tq] = 0; *cnt = 0; }
          }
          tma2d_mc(SBASE + off + rank * 20480, ta, kcol, arow, fb);
          seq++;
        }
        if (op) break;
        if (late && r == 0) continue;
        const int nkv = (late && !offl && r == 3) ? 64 : 32;
#pragma unroll 1
        for (int n = 0; n < nkv; n++) {
          const int head = (n < 32 ? r * 8 : 0) + j;
          const int kvrow = ((2 * p + ((n >> 4) & 1)) * 32 + head) * 512 + ((n >> 1) & 7) * 64;
          const bool special = (n == nkv - 3);
          if (special) mbar_wait(Q0FREE, natt & 1);
          else if (n >= 8) need(seq - 8);
          else if (n < 3) need(seq - n - 4);
          else need(seq - n - 1);
          const uint32_t fb = FULL0 + (seq % NB) * 8;
          mbar_expect_tx(fb, KVSTAGE);
          tma3d_hint(SBASE + (special ? KV_SPECIAL : kv_off(n)), (n & 1) ? tv : tk, 0, kvrow, 0, fb, pol);
          seq++;
        }
        natt++;
      }
    } else if (tid == 416) {
      uint32_t uc = 0;
      uint64_t spol;
      asm volatile("createpolicy.fractional.L2::evict_first.b64 %0, 1.0;" : "=l"(spol));
      uint8_t* qs = reinterpret_cast<uint8_t*>(g_qspill) + (size_t)(blockIdx.x & 63) * QREG;
#pragma unroll 1
      for (int r = 0; r < 4; r++) {
        if (late && r == 0) {
          for (int w = 0; w < 3; w++) mbar_wait(OSTAGED + w * 8, uc & 1);
          uc++;
          for (int c = 0; c < 5; c++) bulk_store(qs + c * 16384, QBASE + c * 16384, 16384);
          bulk_commit();
          bulk_wait0_read();
          mbar_arrive_cluster(QFREE, 0);
          mbar_arrive_cluster(QFREE, 1);
          bulk_wait0();
          fence_async_all();
          if (offl) {
            __threadfence();
            asm volatile("st.release.gpu.global.u32 [%0], 1;" ::"l"(&g_qready[blockIdx.x & 63]) : "memory");
          }
          continue;
        }
        const int nb = (late && !offl && r == 3) ? 4 : 2;
        for (int bb = 0; bb < nb; bb++) {
          const int t = (bb < 2) ? r : 0;
          const int ocol = (t * 8 + j) * 128, orow = blk * ROWS + p * 320;
          for (int w = 0; w < 3; w++) {
            mbar_wait(OSTAGED + w * 8, uc & 1);
            const int np = (w < 2) ? 2 : 1;
            for (int pc = 0; pc < np; pc++) {
              const int rr = (bb & 1) * 160 + w * 64 + pc * 32;
              tma2d_store_hint(&prm.o_st, QBASE + rr * 128, ocol, orow + rr, spol);
              tma2d_store_hint(&prm.o_st, QBASE + (bb == nb - 1 ? -20480 : QHALF) + rr * 128, ocol + 64, orow + rr, spol);
            }
            bulk_commit();
          }
          uc++;
          if (nb == 4 && bb < 2) {
            bulk_wait0_read();
            const uint32_t o = bb * 20480;
            mbar_expect_tx(QLD + bb * 8, 40960);
            bulk_load(QBASE + o, qs + o, 20480, QLD + bb * 8);
            bulk_load(QBASE + QHALF + o, qs + QHALF + o, 20480, QLD + bb * 8);
          }
          if (bb == nb - 2) {
            bulk_wait0_read();
            mbar_arrive(Q0FREE);
          }
          if (bb == nb - 1) {
            bulk_wait0_read();
            mbar_arrive_cluster(QFREE, 0);
            mbar_arrive_cluster(QFREE, 1);
          }
          if (bb & 1) {
            bulk_wait0();
            fence_async_all();
            __threadfence();
            asm volatile("red.release.gpu.global.add.u32 [%0], 1;" ::"l"(&g_cnt[g * 4 + t]) : "memory");
          }
        }
      }
      const int col = blk * 1024 + j * 128, row = p * 320;
      for (int w = 0; w < 3; w++) {
        mbar_wait(OSTAGED + w * 8, uc & 1);
        const int np = (w < 2) ? 4 : 2;
        for (int pc = 0; pc < np; pc++) {
          const int rr = w * 128 + pc * 32;
          tma2d_store(&prm.out_st, QBASE + rr * 128, col, row + rr);
          tma2d_store(&prm.out_st, QBASE + QHALF + rr * 128, col + 64, row + rr);
        }
        bulk_commit();
      }
      bulk_wait0_read();
    }
  } else {
    asm volatile("setmaxnreg.inc.sync.aligned.u32 160;");
    BarSeq bs; bs.cnt = 0;
    const uint32_t rel = make_rel();
    const bool helper = blockIdx.x >= 128;
    const bool late = (blockIdx.x >> 6) == 1;
    const bool offl = late && prm.offload && ((blockIdx.x >> 3) & 7) >= 4;
#pragma unroll 1
    for (int r = helper ? 5 : 0; r <= 5; r++) {
      if (r < 5) {
        const int nst = (r == 4) ? 64 : 16;
        const int nrel = (r == 4) ? nst - 3 : nst + 1;
        if (wg < 2) gemm_phase<2>(bs, nst, nrel, wg * 2, rel);
        else gemm_phase<1>(bs, nst, nrel, 4, rel);
        if (r == 4) { mbar_arrive(OSTAGED + wg * 8); break; }
        bar_sync(BAR_ALL, 384);
      }
      if (late && r == 0) mbar_arrive(OSTAGED + wg * 8);
      else attention_phase(bs, wg, rel, helper ? 16 : ((late && !offl && r == 3) ? 4 : 2), helper);
    }
  }
}

typedef CUresult (*EncodeFn)(CUtensorMap*, CUtensorMapDataType, cuuint32_t, void*, const cuuint64_t*, const cuuint64_t*,
                             const cuuint32_t*, const cuuint32_t*, CUtensorMapInterleave, CUtensorMapSwizzle,
                             CUtensorMapL2promotion, CUtensorMapFloatOOBfill);

static void encode(EncodeFn fn, CUtensorMap* m, const void* ptr, int rank, const cuuint64_t* dims, const cuuint64_t* strides,
                   const cuuint32_t* box) {
  cuuint32_t es[3] = {1, 1, 1};
  CUresult r = fn(m, CU_TENSOR_MAP_DATA_TYPE_BFLOAT16, rank, const_cast<void*>(ptr), dims, strides, box, es,
                  CU_TENSOR_MAP_INTERLEAVE_NONE, CU_TENSOR_MAP_SWIZZLE_128B, CU_TENSOR_MAP_L2_PROMOTION_L2_128B,
                  CU_TENSOR_MAP_FLOAT_OOB_FILL_NONE);
  if (r != CUDA_SUCCESS) fprintf(stderr, "tensor map encode failed: %d\n", (int)r);
}

}

extern "C" void kernel_launch(void* const* d_in, const int* in_sizes, int n_in, void* d_out, int out_size) {
  using namespace mha;
  (void)in_sizes; (void)n_in; (void)out_size;
  static EncodeFn fn = nullptr;
  static void* o_ptr = nullptr;
  static int offload = 0;
  if (!fn) {
    void* f = nullptr;
    cudaDriverEntryPointQueryResult qr;
    cudaGetDriverEntryPoint("cuTensorMapEncodeTiled", &f, cudaEnableDefault, &qr);
    fn = (EncodeFn)f;
    cudaGetSymbolAddress(&o_ptr, g_o);
    cudaFuncSetAttribute(fused_mha_kernel, cudaFuncAttributeMaxDynamicSharedMemorySize, SMEM_BYTES);
    cudaLaunchConfig_t cfg = {};
    cfg.gridDim = dim3(132); cfg.blockDim = dim3(NTHREADS); cfg.dynamicSmemBytes = SMEM_BYTES;
    cudaLaunchAttribute at[1];
    at[0].id = cudaLaunchAttributeClusterDimension;
    at[0].val.clusterDim.x = 2; at[0].val.clusterDim.y = 1; at[0].val.clusterDim.z = 1;
    cfg.attrs = at; cfg.numAttrs = 1;
    int nclusters = 0;
    if (cudaOccupancyMaxActiveClusters(&nclusters, fused_mha_kernel, &cfg) == cudaSuccess && nclusters >= 66) offload = 1;
    (void)cudaGetLastError();
  }
  Params prm;
  for (int b = 0; b < 2; b++) {
    const void* x = d_in[5 * b + 0];
    const void* kc = d_in[5 * b + 1];
    const void* vc = d_in[5 * b + 2];
    const void* wq = d_in[5 * b + 3];
    const void* wo = d_in[5 * b + 4];
    { cuuint64_t d[2] = {1024, 2560}, s[1] = {2048}; cuuint32_t bx[2] = {64, 160};
      encode(fn, &prm.x[b], x, 2, d, s, bx); }
    { cuuint64_t d[3] = {64, 1024, 64}, s[2] = {8192, 128}; cuuint32_t bx[3] = {64, 64, 2};
      encode(fn, &prm.wq[b], wq, 3, d, s, bx); }
    { cuuint64_t d[3] = {64, 262144, 2}, s[2] = {256, 128}; cuuint32_t bx[3] = {64, 64, 2};
      encode(fn, &prm.kc[b], kc, 3, d, s, bx);
      encode(fn, &prm.vc[b], vc, 3, d, s, bx); }
    { cuuint64_t d[3] = {64, 4096, 16}, s[2] = {2048, 128}; cuuint32_t bx[3] = {64, 64, 2};
      encode(fn, &prm.wo[b], wo, 3, d, s, bx); }
  }
  { cuuint64_t d[2] = {4096, 5120}, s[1] = {8192}; cuuint32_t bx[2] = {64, 32};
    encode(fn, &prm.o_st, o_ptr, 2, d, s, bx);
    cuuint32_t bl[2] = {64, 160};
    encode(fn, &prm.o_ld, o_ptr, 2, d, s, bl); }
  { cuuint64_t d[2] = {2048, 2560}, s[1] = {4096}; cuuint32_t bx[2] = {64, 32};
    encode(fn, &prm.out_st, d_out, 2, d, s, bx); }
  prm.offload = offload;
  fused_mha_kernel<<<offload ? 132 : 128, NTHREADS, SMEM_BYTES>>>(prm);
}
```
